```python
import torch

def _softmax(x, axis=-1):
    return torch.softmax(x, dim=axis)
def _gelu(x):
    return torch.nn.functional.gelu(x, approximate="tanh")
def _silu(x):
    return torch.nn.functional.silu(x)
def _sigmoid(x):
    return torch.sigmoid(x)
def _layernorm(x, axis=-1, eps=1e-5):
    m = x.mean(dim=axis, keepdim=True)
    v = x.var(dim=axis, keepdim=True, unbiased=False)
    return (x - m) / torch.sqrt(v + eps)
def _scatter_add(tgt, idx, src, axis=0):
    return tgt.clone().index_add_(axis, idx, src)
def _segment_sum(src, seg, n):
    out = torch.zeros((n,) + src.shape[1:], dtype=src.dtype)
    return out.index_add_(0, seg, src)
def _pad(x, pw):
    flat = tuple(v for pair in reversed(pw) for v in pair)
    return torch.nn.functional.pad(x, flat)

kernel_name = 'parallel_sum__mha_block_cached__mixer_token_mlp__decode'

def setup_inputs():

    _w = (lambda a: (lambda t: t.to(torch.bfloat16) if t.is_floating_point() else t)(torch.as_tensor(a)))
    def _A_setup():
        B, Sq, D = 1, 1, 640
        H, Sk, Dh = 32, 32768, 128
        return {
            "x": _w((lambda *s: torch.randn(*s, dtype=torch.bfloat16) * 0.05)(B, Sq, D)),
            "k_cache": _w((lambda *s: torch.randn(*s, dtype=torch.bfloat16) * 3.2)(B, H, Sk, Dh)),
            "v_cache": _w((lambda *s: torch.randn(*s, dtype=torch.bfloat16) * 0.8)(B, H, Sk, Dh)),
            "wq": _w((lambda *s: torch.randn(*s, dtype=torch.bfloat16) * 3.2)(D, H * Dh) * (D ** -0.5)),
            "wo": _w((lambda *s: torch.randn(*s, dtype=torch.bfloat16) * 0.8)(H * Dh, D) * ((H * Dh) ** -0.5)),
        }
    _A_in = _A_setup()

    def _B_setup():
        B, S, D, F = 1, 1, 640, 1728
        return {
            "x": _w((lambda *s: torch.randn(*s, dtype=torch.bfloat16) * 0.05)(B, S, D)),
            "w1": _w((lambda *s: torch.randn(*s, dtype=torch.bfloat16) * 0.8)(S, F) * (S ** -0.5)),
            "b1": _w((lambda *s: torch.randn(*s, dtype=torch.bfloat16) * 0.8)(F) * 0.02),
            "w2": _w((lambda *s: torch.randn(*s, dtype=torch.bfloat16) * 0.8)(F, S) * (F ** -0.5)),
            "b2": _w((lambda *s: torch.randn(*s, dtype=torch.bfloat16) * 0.8)(S) * 0.02),
        }
    _B_in = _B_setup()

    return {
        "A_x": _A_in["x"],
        "A_k_cache": _A_in["k_cache"],
        "A_v_cache": _A_in["v_cache"],
        "A_wq": _A_in["wq"],
        "A_wo": _A_in["wo"],
        "B_x": _B_in["x"],
        "B_w1": _B_in["w1"],
        "B_b1": _B_in["b1"],
        "B_w2": _B_in["w2"],
        "B_b2": _B_in["b2"],
    }

def reference(A_x, A_k_cache, A_v_cache, A_wq, A_wo, B_x, B_w1, B_b1, B_w2, B_b2):
    def _A_ref(x, k_cache, v_cache, wq, wo):
        B, Sq, D = x.shape
        H, Dh = 32, 128
        q = (lambda x, *d: x.permute(*d))((x @ wq).reshape(B, Sq, H, Dh), 0, 2, 1, 3)
        scores = torch.einsum("bhqd,bhkd->bhqk", q, k_cache) * (Dh ** -0.5)
        p = _softmax(scores, axis=-1)
        o = torch.einsum("bhqk,bhkd->bhqd", p, v_cache)
        return (lambda x, *d: x.permute(*d))(o, 0, 2, 1, 3).reshape(B, Sq, H * Dh) @ wo

    def _B_ref(x, w1, b1, w2, b2):
        B, S, D = x.shape
        h = _layernorm(x, axis=-1)
        u = torch.einsum("bsd,sf->bdf", h, w1) + b1
        u = _gelu(u)
        y = torch.einsum("bdf,fs->bds", u, w2) + b2
        return (lambda x, *d: x.permute(*d))(y, 0, 2, 1)

    x = A_x
    xn = _layernorm(x, axis=-1)
    return x + _A_ref(xn, A_k_cache, A_v_cache, A_wq, A_wo) + _B_ref(xn, B_w1, B_b1, B_w2, B_b2)
```

```cpp
#include <cuda.h>
#include <cuda_runtime.h>
#include <cuda_bf16.h>
#include <stdint.h>

namespace {

constexpr int D_MODEL = 640;
constexpr int NHEAD = 32;
constexpr int SK = 32768;
constexpr int DH = 128;
constexpr int FDIM = 1728;

#define CFG_HPG 2
#define CFG_STAGES 10
#define CFG_INFLIGHT 3
#define CFG_WQ_PREFETCH 0
#define CFG_TOP_PREFETCH 0
#define CFG_LEAD (CPG / 2)
#define CFG_FEEDBACK 1
#define CFG_WO_AT 32
#define CFG_WO_EARLY 0
#define CFG_WO_PF 0
#define CFG_WO_WARM 0
#define CFG_WO_THRESH 64

constexpr int HPG = CFG_HPG;
constexpr int NGROUP = NHEAD / HPG;
constexpr int CPG = 4 * HPG;
constexpr int NCTA = NGROUP * CPG;
constexpr int STAGES = CFG_STAGES;
constexpr int INFLIGHT = CFG_INFLIGHT;

constexpr int TILE_KEYS = 64;
constexpr int TILE_BYTES = TILE_KEYS * DH * 2;
constexpr int ITEMS_PER_HEAD = SK / TILE_KEYS;
constexpr int ITEMS_PER_GROUP = ITEMS_PER_HEAD * HPG;
constexpr int NSTATIC = 2;

constexpr int NCONS_WARPS = 4;
constexpr int NAUX_WARPS = 5;
constexpr int NTHREADS = (NCONS_WARPS + 1 + NAUX_WARPS) * 32;
constexpr int PRODUCER_TID = NCONS_WARPS * 32;
constexpr int CONS_AUX = (NCONS_WARPS + NAUX_WARPS) * 32;

constexpr int WO_COLS = D_MODEL / 4;
constexpr int W_BYTES = D_MODEL * 64;
constexpr int RED_STRIDE = 136;
constexpr int REC_WORDS = 132;

constexpr int SM_RING = 0;
constexpr int SM_W = SM_RING + STAGES * TILE_BYTES;
constexpr int SM_RED = SM_W + W_BYTES;
constexpr int SM_XN = SM_RED + 16 * RED_STRIDE * 4;
constexpr int SM_Q = SM_XN + D_MODEL * 2;
constexpr int SM_O = SM_Q + HPG * DH * 2;
constexpr int SM_STAT = SM_O + DH * 2;
constexpr int SM_META = SM_STAT + 64;
constexpr int SM_BAR = SM_META + 64;
constexpr int SM_TOTAL = SM_BAR + (2 * STAGES + 3) * 8;
static_assert(INFLIGHT + 1 < STAGES && INFLIGHT <= 2 * NSTATIC, "window");
static_assert(STAGES <= 16, "meta size");

constexpr float LOG2E = 1.4426950408889634f;
constexpr float SCORE_SCALE = 0.08838834764831845f;
constexpr float LN_EPS = 1.0013580322265625e-05f;
constexpr unsigned SPIN_LIMIT = 1u << 24;

__device__ unsigned g_epoch;
__device__ unsigned g_total;
__device__ unsigned g_done;
__device__ unsigned g_queue[NGROUP * 32];
__device__ unsigned long long g_q[NHEAD * DH];
__device__ unsigned long long g_rec[NHEAD * CPG * REC_WORDS];
__device__ unsigned long long g_y[NHEAD * D_MODEL];

#define TL(k) do { } while (0)

__device__ __forceinline__ uint32_t smem_u32(const void* p) { return (uint32_t)__cvta_generic_to_shared(p); }

__device__ __forceinline__ void mbar_init(uint32_t bar, uint32_t cnt) {
    asm volatile("mbarrier.init.shared::cta.b64 [%0], %1;" ::"r"(bar), "r"(cnt) : "memory");
}
__device__ __forceinline__ void mbar_expect_tx(uint32_t bar, uint32_t bytes) {
    asm volatile("mbarrier.arrive.expect_tx.shared::cta.b64 _, [%0], %1;" ::"r"(bar), "r"(bytes) : "memory");
}
__device__ __forceinline__ void mbar_arrive(uint32_t bar) {
    asm volatile("mbarrier.arrive.shared::cta.b64 _, [%0];" ::"r"(bar) : "memory");
}
__device__ __forceinline__ bool mbar_try(uint32_t bar, uint32_t parity) {
    uint32_t ok;
    asm volatile("{\n.reg .pred p;\nmbarrier.try_wait.parity.shared::cta.b64 p, [%1], %2;\nselp.u32 %0, 1, 0, p;\n}"
                 : "=r"(ok) : "r"(bar), "r"(parity) : "memory");
    return ok != 0;
}
__device__ __forceinline__ void mbar_wait(uint32_t bar, uint32_t parity) {
    unsigned n = 0;
    while (!mbar_try(bar, parity)) {
        if (++n > SPIN_LIMIT) __trap();
    }
}
__device__ __forceinline__ void bulk_g2s(uint32_t dst, const void* src, uint32_t bytes, uint32_t bar, uint64_t pol) {
    asm volatile(
        "cp.async.bulk.shared::cluster.global.mbarrier::complete_tx::bytes.L2::cache_hint [%0], [%1], %2, [%3], %4;"
        ::"r"(dst), "l"(src), "r"(bytes), "r"(bar), "l"(pol) : "memory");
}
__device__ __forceinline__ void tma_load_2d(uint32_t dst, const CUtensorMap* map, int c0, int c1, uint32_t bar) {
    asm volatile("cp.async.bulk.tensor.2d.shared::cluster.global.mbarrier::complete_tx::bytes [%0], [%1, {%3, %4}], [%2];"
                 ::"r"(dst), "l"(map), "r"(bar), "r"(c0), "r"(c1) : "memory");
}
__device__ __forceinline__ void bulk_prefetch_l2(const void* src, uint32_t bytes) {
    asm volatile("cp.async.bulk.prefetch.L2.global [%0], %1;" ::"l"(src), "r"(bytes) : "memory");
}
__device__ __forceinline__ uint32_t ldg32(const void* p) {
    uint32_t v;
    asm volatile("ld.global.nc.u32 %0, [%1];" : "=r"(v) : "l"(p));
    return v;
}
__device__ __forceinline__ void cp_async16(uint32_t dst, const void* src) {
    asm volatile("cp.async.cg.shared.global [%0], [%1], 16;" ::"r"(dst), "l"(src) : "memory");
}
__device__ __forceinline__ void named_sync(int id, int n) { asm volatile("bar.sync %0, %1;" ::"r"(id), "r"(n) : "memory"); }
__device__ __forceinline__ void named_arrive(int id, int n) { asm volatile("bar.arrive %0, %1;" ::"r"(id), "r"(n) : "memory"); }

__device__ __forceinline__ uint4 lds128(uint32_t a) {
    uint4 v;
    asm volatile("ld.shared.v4.u32 {%0,%1,%2,%3}, [%4];" : "=r"(v.x), "=r"(v.y), "=r"(v.z), "=r"(v.w) : "r"(a));
    return v;
}
__device__ __forceinline__ uint32_t lds32(uint32_t a) {
    uint32_t v;
    asm volatile("ld.shared.u32 %0, [%1];" : "=r"(v) : "r"(a));
    return v;
}
__device__ __forceinline__ void ldsm4t(uint32_t (&r)[4], uint32_t a) {
    asm volatile("ldmatrix.sync.aligned.m8n8.x4.trans.shared.b16 {%0,%1,%2,%3}, [%4];"
                 : "=r"(r[0]), "=r"(r[1]), "=r"(r[2]), "=r"(r[3]) : "r"(a));
}
__device__ __forceinline__ void ldsm2t(uint32_t (&r)[2], uint32_t a) {
    asm volatile("ldmatrix.sync.aligned.m8n8.x2.trans.shared.b16 {%0,%1}, [%2];" : "=r"(r[0]), "=r"(r[1]) : "r"(a));
}
__device__ __forceinline__ void mma16816(float (&c)[4], uint32_t a0, uint32_t a1, uint32_t a2, uint32_t a3, uint32_t b0, uint32_t b1) {
    asm volatile(
        "mma.sync.aligned.m16n8k16.row.col.f32.bf16.bf16.f32 {%0,%1,%2,%3}, {%4,%5,%6,%7}, {%8,%9}, {%0,%1,%2,%3};"
        : "+f"(c[0]), "+f"(c[1]), "+f"(c[2]), "+f"(c[3]) : "r"(a0), "r"(a1), "r"(a2), "r"(a3), "r"(b0), "r"(b1));
}
__device__ __forceinline__ float bf16r(float x) { return __bfloat162float(__float2bfloat16_rn(x)); }
__device__ __forceinline__ float bf_lo(uint32_t v) { return __uint_as_float(v << 16); }
__device__ __forceinline__ float bf_hi(uint32_t v) { return __uint_as_float(v & 0xffff0000u); }
__device__ __forceinline__ uint32_t pack_bf16(float lo, float hi) {
    uint32_t r;
    asm("cvt.rn.bf16x2.f32 %0, %1, %2;" : "=r"(r) : "f"(hi), "f"(lo));
    return r;
}
__device__ __forceinline__ float ex2(float x) { float y; asm("ex2.approx.ftz.f32 %0, %1;" : "=f"(y) : "f"(x)); return y; }
__device__ __forceinline__ float rcp(float x) { float y; asm("rcp.approx.ftz.f32 %0, %1;" : "=f"(y) : "f"(x)); return y; }

__device__ __forceinline__ void st_word(unsigned long long* p, float v, unsigned label) {
    unsigned long long w = ((unsigned long long)label << 32) | __float_as_uint(v);
    asm volatile("st.relaxed.gpu.global.b64 [%0], %1;" ::"l"(p), "l"(w) : "memory");
}
__device__ __forceinline__ void st_word2(unsigned long long* p, float v0, float v1, unsigned label) {
    const unsigned long long w0 = ((unsigned long long)label << 32) | __float_as_uint(v0);
    const unsigned long long w1 = ((unsigned long long)label << 32) | __float_as_uint(v1);
    asm volatile("st.relaxed.gpu.global.v2.b64 [%0], {%1, %2};" ::"l"(p), "l"(w0), "l"(w1) : "memory");
}
__device__ __forceinline__ unsigned long long ld_word(const unsigned long long* p) {
    unsigned long long w;
    asm volatile("ld.relaxed.gpu.global.b64 %0, [%1];" : "=l"(w) : "l"(p) : "memory");
    return w;
}
__device__ __forceinline__ float word_value(unsigned long long w) { return __uint_as_float((unsigned)w); }
__device__ __forceinline__ unsigned word_label(unsigned long long w) { return (unsigned)(w >> 32); }

__device__ __forceinline__ float warp_sum(float v) {
#pragma unroll
    for (int o = 16; o > 0; o >>= 1) v += __shfl_xor_sync(0xffffffffu, v, o);
    return v;
}

struct LnStat { float mean, den; };
__device__ __forceinline__ float ln_apply(float x, LnStat st) { return bf16r(__fdiv_rn(bf16r(x - st.mean), st.den)); }
__device__ __forceinline__ LnStat warp_layernorm(float (&v)[20]) {
    float s = 0.f;
#pragma unroll
    for (int i = 0; i < 20; i++) s += v[i];
    const float mean = warp_sum(s) / (float)D_MODEL;
    float ss = 0.f;
#pragma unroll
    for (int i = 0; i < 20; i++) { float d = v[i] - mean; ss += d * d; }
    const float var = bf16r(warp_sum(ss) / (float)D_MODEL);
    LnStat st;
    st.mean = bf16r(mean);
    st.den = bf16r(sqrtf(bf16r(var + LN_EPS)));
#pragma unroll
    for (int i = 0; i < 20; i++) v[i] = ln_apply(v[i], st);
    return st;
}

struct Params {
    CUtensorMap wo_map;
    const __nv_bfloat16 *x, *k, *v, *wq, *wo, *w1, *b1, *w2, *b2;
    __nv_bfloat16* out;
};

template <bool LAST>
__device__ __forceinline__ void flush_record(unsigned char* smem, int head, int r, unsigned tag16, int warp, int lane, int tid,
                                             float (&acc)[8][4], float m, float l) {
    float* red = reinterpret_cast<float*>(smem + SM_RED);
    float* stat = reinterpret_cast<float*>(smem + SM_STAT);
    const int g = lane >> 2, t = lane & 3;
    l += __shfl_xor_sync(0xffffffffu, l, 4);
    float* row = red + (warp * 4 + t) * RED_STRIDE + g;
#pragma unroll
    for (int c = 0; c < 8; c++) {
        const int ch = (c ^ (2 * t)) * 8;
        row[ch] = acc[c][0] + acc[c ^ 1][1];
        row[64 + ch] = acc[c][2] + acc[c ^ 1][3];
    }
    l += __shfl_xor_sync(0xffffffffu, l, 8);
    l += __shfl_xor_sync(0xffffffffu, l, 16);
    if (lane == 0) { stat[warp] = m; stat[4 + warp] = l; }
    named_sync(1, 128);
    float mw[4], M = -INFINITY;
#pragma unroll
    for (int w = 0; w < 4; w++) { mw[w] = stat[w]; M = fmaxf(M, mw[w]); }
    const float ML = (M == -INFINITY) ? 0.f : __fmul_rn(M, LOG2E);
    float o = 0.f, L = 0.f;
#pragma unroll
    for (int w = 0; w < 4; w++) {
        const float f = ex2(__fmul_rn(mw[w], LOG2E) - ML);
        float s = 0.f;
#pragma unroll
        for (int tt = 0; tt < 4; tt++) s += red[(w * 4 + tt) * RED_STRIDE + tid];
        o += f * s;
        L += f * stat[4 + w];
    }
    const unsigned label = (tag16 << 16) | (__float_as_uint(M) >> 16);
    unsigned long long* rec = g_rec + (size_t)(head * CPG + r) * REC_WORDS;
    st_word(rec + tid, o, label);
    if (tid == 0) st_word(rec + 128, L, label);
    if (!LAST) named_sync(1, 128);
}

__global__ void __launch_bounds__(NTHREADS, 1) fused_decode_kernel(const __grid_constant__ Params p) {
    extern __shared__ __align__(1024) unsigned char smem[];
    const int tid = threadIdx.x, warp = tid >> 5, lane = tid & 31;
    const int group = blockIdx.x / CPG, r = blockIdx.x % CPG;
    const uint32_t sbase = smem_u32(smem);
    const uint32_t bar_full = sbase + SM_BAR, bar_empty = bar_full + STAGES * 8;
    const uint32_t bar_wq = bar_empty + STAGES * 8, bar_wo = bar_wq + 8, bar_wfree = bar_wo + 8;
    volatile int* meta = reinterpret_cast<volatile int*>(smem + SM_META);
    const unsigned char* kg = reinterpret_cast<const unsigned char*>(p.k) + (size_t)group * HPG * SK * DH * 2;
    const unsigned char* vg = reinterpret_cast<const unsigned char*>(p.v) + (size_t)group * HPG * SK * DH * 2;
    uint64_t pol;
    asm volatile("createpolicy.fractional.L2::evict_first.b64 %0, 1.0;" : "=l"(pol));

    if (warp == NCONS_WARPS) {
        if (lane == 0) {
            TL(0);
            for (int s = 0; s < STAGES; s++) { mbar_init(bar_full + s * 8, 1); mbar_init(bar_empty + s * 8, NCONS_WARPS); }
            mbar_init(bar_wq, NAUX_WARPS * 32); mbar_init(bar_wo, 1); mbar_init(bar_wfree, NCONS_WARPS);
            asm volatile("fence.mbarrier_init.release.cluster;" ::: "memory");
            asm volatile("fence.proxy.async.shared::cta;" ::: "memory");
#pragma unroll
            for (int n = 0; n < INFLIGHT; n++) {
                const int item = r + (n >> 1) * CPG;
                meta[n] = item;
                mbar_expect_tx(bar_full + n * 8, TILE_BYTES);
                bulk_g2s(sbase + SM_RING + n * TILE_BYTES, ((n & 1) ? vg : kg) + (size_t)item * TILE_BYTES, TILE_BYTES, bar_full + n * 8, pol);
            }
            TL(14);
        }
        __syncwarp();
        named_arrive(5, (NCONS_WARPS + 1) * 32);
        named_arrive(6, (NAUX_WARPS + 1) * 32);
        if (lane == 0) {
            unsigned* queue = g_queue + group * 32;
            unsigned next = atomicAdd(queue, 1u) + NSTATIC * CPG;
            unsigned total = atomicAdd(&g_total, 1u);
            int n = INFLIGHT;
            int window = INFLIGHT;
            auto issue = [&](const unsigned char* src, int item) {
                const int s = n % STAGES;
                const int q = max(n - window, 0);
                mbar_wait(bar_full + (q % STAGES) * 8, (q / STAGES) & 1);
                if (n >= STAGES) mbar_wait(bar_empty + s * 8, ((n / STAGES) - 1) & 1);
                meta[s] = item;
                mbar_expect_tx(bar_full + s * 8, TILE_BYTES);
                bulk_g2s(sbase + SM_RING + s * TILE_BYTES, src, TILE_BYTES, bar_full + s * 8, pol);
                n++;
            };
            bool wo_armed = false;
            auto issue_wo = [&](int first, int last) {
                if (!wo_armed) { mbar_wait(bar_wfree, 0); mbar_expect_tx(bar_wo, W_BYTES); wo_armed = true; }
#pragma unroll 1
                for (int i = first; i < last; i++)
                    tma_load_2d(sbase + SM_W + i * DH * 64, &p.wo_map, (r & 3) * WO_COLS + i * 32, (group * HPG + (r >> 2)) * DH, bar_wo);
            };
            int wo_boxes = 0;
            bool wo_warm = false;
#pragma unroll 1
            while (n < 2 * NSTATIC) {
                const int item = r + (n >> 1) * CPG;
                issue(((n & 1) ? vg : kg) + (size_t)item * TILE_BYTES, item);
            }
#pragma unroll 1
            while (next < (unsigned)ITEMS_PER_GROUP) {
                const unsigned item = next;
                if (CFG_WO_WARM > 0 && !wo_warm && item + CFG_WO_WARM * CPG >= (unsigned)ITEMS_PER_GROUP) {
                    wo_warm = true;
                    asm volatile("prefetch.tensormap [%0];" ::"l"(&p.wo_map) : "memory");
                    const unsigned char* wsl = reinterpret_cast<const unsigned char*>(p.wo) + ((size_t)(group * HPG + (r >> 2)) * DH * D_MODEL + (r & 3) * WO_COLS) * 2;
                    bulk_prefetch_l2(wsl, 64);
                    bulk_prefetch_l2(wsl + (size_t)(DH - 1) * D_MODEL * 2, 64);
                }
                if (n == CFG_WO_AT && CFG_WO_EARLY > 0) { issue_wo(0, CFG_WO_EARLY); wo_boxes = CFG_WO_EARLY; }
                {
                    const int lead = (int)(item - NSTATIC * CPG) - (int)(total / NGROUP);
                    window = INFLIGHT + (lead > CFG_LEAD ? -1 : (lead < -CFG_LEAD ? 1 : 0));
                }
                next = atomicAdd(queue, 1u) + NSTATIC * CPG;
                total = atomicAdd(&g_total, 1u);
                issue(kg + (size_t)item * TILE_BYTES, (int)item);
                issue(vg + (size_t)item * TILE_BYTES, (int)item);
            }
            TL(5);
            const int s = n % STAGES;
            if (n >= STAGES) mbar_wait(bar_empty + s * 8, ((n / STAGES) - 1) & 1);
            meta[s] = -1;
            mbar_arrive(bar_full + s * 8);
            if (wo_boxes < 5) {
                if (CFG_WO_THRESH > 0) {
                    unsigned done = atomicAdd(&g_done, 1u) + 1, spins = 0;
                    while (done < (unsigned)CFG_WO_THRESH) {
                        done = *reinterpret_cast<volatile unsigned*>(&g_done);
                        if (++spins > SPIN_LIMIT) __trap();
                    }
                }
                if (CFG_WO_PF)
                    bulk_prefetch_l2(reinterpret_cast<const unsigned char*>(p.wo) + ((size_t)(group * HPG + (r >> 2)) * DH + (r & 3) * 32) * D_MODEL * 2,
                                     32 * D_MODEL * 2);
                issue_wo(wo_boxes, 5);
                TL(12);
            }
        }
    } else if (warp < NCONS_WARPS) {
        const int g = lane >> 2, t = lane & 3, par = g & 1;
        unsigned tag;
        {
            uint32_t xr[10];
#pragma unroll
            for (int i = 0; i < 10; i++) xr[i] = ldg32(reinterpret_cast<const uint32_t*>(p.x) + lane + 32 * i);
            tag = *reinterpret_cast<volatile unsigned*>(&g_epoch) + 1;
            if (warp == 0) st_word(g_q + group * HPG * DH + r * 32 + lane, 0.f, 0u);
#pragma unroll
            for (int e = 0; e < HPG; e++) {
                unsigned long long* rec = g_rec + (size_t)((group * HPG + e) * CPG + r) * REC_WORDS;
                st_word(rec + tid, 0.f, 0u);
                if (tid < REC_WORDS - 128) st_word(rec + 128 + tid, 0.f, 0u);
            }
            if (tid < WO_COLS / 2) st_word2(g_y + (group * HPG + (r >> 2)) * D_MODEL + (r & 3) * WO_COLS + 2 * tid, 0.f, 0.f, 0u);
            float xv[20];
#pragma unroll
            for (int i = 0; i < 10; i++) { xv[2 * i] = bf_lo(xr[i]); xv[2 * i + 1] = bf_hi(xr[i]); }
            warp_layernorm(xv);
            if (warp == 0) {
#pragma unroll
                for (int i = 0; i < 10; i++)
                    reinterpret_cast<uint32_t*>(smem + SM_XN)[lane + 32 * i] = pack_bf16(xv[2 * i], xv[2 * i + 1]);
            }
            if (tid == 0) TL(1);
            named_sync(5, (NCONS_WARPS + 1) * 32);
            mbar_wait(bar_wq, 0);
            if (tid == 0) TL(2);
            float c[4][4];
#pragma unroll
            for (int i = 0; i < 4; i++) { c[i][0] = c[i][1] = c[i][2] = c[i][3] = 0.f; }
            const uint32_t xa = sbase + SM_XN + t * 4;
#pragma unroll
            for (int kk = 0; kk < 20; kk++) {
                const int row = kk * 32 + lane;
                uint32_t b[4];
                ldsm4t(b, sbase + SM_W + row * 64 + ((warp ^ ((row >> 1) & 3)) << 4));
                const uint32_t a0 = lds32(xa + kk * 64), a2 = lds32(xa + kk * 64 + 16);
                const uint32_t a4 = lds32(xa + kk * 64 + 32), a6 = lds32(xa + kk * 64 + 48);
                mma16816(c[(2 * kk) & 3], a0, a0, a2, a2, b[0], b[1]);
                mma16816(c[(2 * kk + 1) & 3], a4, a4, a6, a6, b[2], b[3]);
            }
            __syncwarp();
            if (lane == 0) mbar_arrive(bar_wfree);
            if (g == 0) {
                unsigned long long* dst = g_q + group * HPG * DH + r * 32 + warp * 8 + 2 * t;
                st_word(dst, bf16r(c[0][0] + c[1][0] + c[2][0] + c[3][0]), tag);
                st_word(dst + 1, bf16r(c[0][1] + c[1][1] + c[2][1] + c[3][1]), tag);
            }
            if (tid == 0) TL(3);
            const unsigned long long* qsrc = g_q + group * HPG * DH + tid;
            unsigned long long w[HPG];
#pragma unroll
            for (int i = 0; i < HPG; i++) w[i] = ld_word(qsrc + i * DH);
            for (unsigned n = 0;; n++) {
                bool ok = true;
#pragma unroll
                for (int i = 0; i < HPG; i++) {
                    if (word_label(w[i]) != tag) { w[i] = ld_word(qsrc + i * DH); ok = false; }
                }
                if (__all_sync(0xffffffffu, ok)) break;
                if (n > SPIN_LIMIT) __trap();
            }
#pragma unroll
            for (int i = 0; i < HPG; i++)
                reinterpret_cast<__nv_bfloat16*>(smem + SM_Q)[i * DH + tid] = __float2bfloat16_rn(word_value(w[i]));
            named_sync(1, 128);
        }
        if (tid == 0) TL(4);
        const unsigned tag16 = tag % 65535u + 1u;

        const uint32_t koff = SM_RING + (warp * 16 + g) * 256 + (par << 6) + t * 16;
        const uint32_t voff = SM_RING + (warp * 16 + (lane & 7) + 8 * (lane >> 4)) * 256 + ((lane >> 3) & 1) * 128 + (lane & 7) * 16;
        const bool diag = (t == (g >> 1));
        const uint32_t sel0 = diag ? (par ? 0x1044u : 0x4410u) : 0x4444u;
        const uint32_t sel1 = diag ? (par ? 0x3244u : 0x4432u) : 0x4444u;

        float acc[8][4];
        uint32_t qf[4][4];
        float m = -INFINITY, mL = 0.f, l = 0.f;
        int cur = -1;
        int s = 0;
        uint32_t ph = 0;
#pragma unroll 1
        while (true) {
            mbar_wait(bar_full + s * 8, ph);
            const int item = meta[s];
            if (item < 0) break;
            const int hh = item / ITEMS_PER_HEAD;
            if (hh != cur) {
                if (cur >= 0) flush_record<false>(smem, group * HPG + cur, r, tag16, warp, lane, tid, acc, m, l);
#pragma unroll
                for (int c = 0; c < 8; c++) { acc[c][0] = acc[c][1] = acc[c][2] = acc[c][3] = 0.f; }
                m = -INFINITY; mL = 0.f; l = 0.f;
                for (int e = cur + 1; e < hh; e++) flush_record<false>(smem, group * HPG + e, r, tag16, warp, lane, tid, acc, m, l);
                cur = hh;
#pragma unroll
                for (int u = 0; u < 4; u++) {
                    const uint4 v = lds128(sbase + SM_Q + hh * 256 + (((par << 6) + t * 16) ^ (u << 6)));
                    qf[u][0] = v.x; qf[u][1] = v.y; qf[u][2] = v.z; qf[u][3] = v.w;
                }
            }
            const uint32_t ka = sbase + s * TILE_BYTES + koff;
            uint4 x[4], y[4];
#pragma unroll
            for (int u = 0; u < 4; u++) { x[u] = lds128(ka ^ (u << 6)); y[u] = lds128((ka ^ (u << 6)) + 2048); }
            float c0[4] = {0.f, 0.f, 0.f, 0.f}, c1[4] = {0.f, 0.f, 0.f, 0.f};
#pragma unroll
            for (int u = 0; u < 4; u++) {
                mma16816(c0, x[u].x, y[u].x, x[u].y, y[u].y, qf[u][0], qf[u][1]);
                mma16816(c1, x[u].z, y[u].z, x[u].w, y[u].w, qf[u][2], qf[u][3]);
            }
            __syncwarp();
            if (lane == 0) mbar_arrive(bar_empty + s * 8);
            if (++s == STAGES) { s = 0; ph ^= 1; }

            float s_lo = par ? (c0[1] + c1[1]) : (c0[0] + c1[0]);
            float s_hi = par ? (c0[3] + c1[3]) : (c0[2] + c1[2]);
            {
                uint32_t pk = pack_bf16(s_lo, s_hi);
                pk = pack_bf16(bf_lo(pk) * SCORE_SCALE, bf_hi(pk) * SCORE_SCALE);
                s_lo = bf_lo(pk); s_hi = bf_hi(pk);
            }
            const float mx = fmaxf(s_lo, s_hi);
            if (__any_sync(0xffffffffu, mx > m)) {
                float mn = fmaxf(mx, m);
                mn = fmaxf(mn, __shfl_xor_sync(0xffffffffu, mn, 4));
                mn = fmaxf(mn, __shfl_xor_sync(0xffffffffu, mn, 8));
                mn = fmaxf(mn, __shfl_xor_sync(0xffffffffu, mn, 16));
                const float mLn = __fmul_rn(mn, LOG2E);
                const float sc = (m == -INFINITY) ? 0.f : ex2(mL - mLn);
#pragma unroll
                for (int c = 0; c < 8; c++) { acc[c][0] *= sc; acc[c][1] *= sc; acc[c][2] *= sc; acc[c][3] *= sc; }
                l *= sc;
                m = mn; mL = mLn;
            }
            const float p_lo = ex2(fmaf(s_lo, LOG2E, -mL));
            const float p_hi = ex2(fmaf(s_hi, LOG2E, -mL));
            l += p_lo + p_hi;
            const uint32_t pk = pack_bf16(p_lo, p_hi);
            const uint32_t b0 = __byte_perm(pk, 0, sel0), b1 = __byte_perm(pk, 0, sel1);

            mbar_wait(bar_full + s * 8, ph);
            const uint32_t va = sbase + s * TILE_BYTES + voff;
#pragma unroll
            for (int c = 0; c < 8; c++) {
                uint32_t a[4];
                ldsm4t(a, va ^ (c << 4));
                mma16816(acc[c], a[0], a[1], a[2], a[3], b0, b1);
            }
            __syncwarp();
            if (lane == 0) mbar_arrive(bar_empty + s * 8);
            if (++s == STAGES) { s = 0; ph ^= 1; }
        }
        if (tid == 0) TL(6);
        named_arrive(2, CONS_AUX);
        if (HPG == 1) {
            flush_record<true>(smem, group, r, tag16, warp, lane, tid, acc, m, l);
        } else {
            if (cur >= 0) flush_record<false>(smem, group * HPG + cur, r, tag16, warp, lane, tid, acc, m, l);
#pragma unroll
            for (int c = 0; c < 8; c++) { acc[c][0] = acc[c][1] = acc[c][2] = acc[c][3] = 0.f; }
            for (int e = cur + 1; e < HPG; e++) flush_record<false>(smem, group * HPG + e, r, tag16, warp, lane, tid, acc, -INFINITY, 0.f);
        }
        if (tid == 0) TL(7);

        const int head = group * HPG + (r >> 2), j = r & 3;
        const unsigned long long* rec = g_rec + (size_t)head * CPG * REC_WORDS;
        unsigned long long wo_[CPG], wl[CPG];
#pragma unroll
        for (int i = 0; i < CPG; i++) { wo_[i] = ld_word(rec + i * REC_WORDS + tid); wl[i] = ld_word(rec + i * REC_WORDS + 128); }
        uint32_t bw[8][10];
        auto load_wo_frags = [&]() {
            uint32_t wa[3];
#pragma unroll
            for (int i = 0; i < 3; i++) {
                const int nt = min(warp * 5 + 2 * i + (lane >> 4), 19), row = lane & 15;
                wa[i] = sbase + SM_W + (nt >> 2) * (DH * 64) + row * 64 + (((nt & 3) ^ ((row >> 1) & 3)) << 4);
            }
#pragma unroll
            for (int ks = 0; ks < 8; ks++) {
                uint32_t b[4], b2[2];
                ldsm4t(b, wa[0] + ks * 16 * 64);
                bw[ks][0] = b[0]; bw[ks][1] = b[1]; bw[ks][2] = b[2]; bw[ks][3] = b[3];
                ldsm4t(b, wa[1] + ks * 16 * 64);
                bw[ks][4] = b[0]; bw[ks][5] = b[1]; bw[ks][6] = b[2]; bw[ks][7] = b[3];
                ldsm2t(b2, wa[2] + ks * 16 * 64);
                bw[ks][8] = b2[0]; bw[ks][9] = b2[1];
            }
        };
        const bool wo_early = __all_sync(0xffffffffu, mbar_try(bar_wo, 0));
        if (wo_early) load_wo_frags();
        unsigned long long* ydst = g_y + head * D_MODEL + j * WO_COLS + warp * 40 + g * 8 + 2 * t;
        for (unsigned n = 0;; n++) {
            bool ok = true;
#pragma unroll
            for (int i = 0; i < CPG; i++) {
                if ((word_label(wo_[i]) >> 16) != tag16) { wo_[i] = ld_word(rec + i * REC_WORDS + tid); ok = false; }
                if ((word_label(wl[i]) >> 16) != tag16) { wl[i] = ld_word(rec + i * REC_WORDS + 128); ok = false; }
            }
            if (__all_sync(0xffffffffu, ok)) break;
            if (n > SPIN_LIMIT) __trap();
        }
        if (tid == 0) TL(8);
        if (r == CPG - 4 && tid == 0) g_queue[group * 32] = 0;
        {
            float M = -INFINITY;
#pragma unroll
            for (int i = 0; i < CPG; i++) M = fmaxf(M, __uint_as_float(word_label(wo_[i]) << 16));
            const float ML = __fmul_rn(M, LOG2E);
            float o = 0.f, L = 0.f;
#pragma unroll
            for (int i = 0; i < CPG; i++) {
                const float f = ex2(__fmul_rn(__uint_as_float(word_label(wo_[i]) << 16), LOG2E) - ML);
                o = fmaf(f, word_value(wo_[i]), o);
                L = fmaf(f, word_value(wl[i]), L);
            }
            reinterpret_cast<__nv_bfloat16*>(smem + SM_O)[tid] = __float2bfloat16_rn(__fdiv_rn(o, L));
        }
        named_sync(1, 128);
        if (tid == 0) TL(9);
        if (!wo_early) { mbar_wait(bar_wo, 0); load_wo_frags(); }
        if (tid == 0) TL(10);
        float y[2][5][4];
#pragma unroll
        for (int i = 0; i < 5; i++) {
            y[0][i][0] = y[0][i][1] = y[0][i][2] = y[0][i][3] = 0.f;
            y[1][i][0] = y[1][i][1] = y[1][i][2] = y[1][i][3] = 0.f;
        }
#pragma unroll
        for (int ks = 0; ks < 8; ks++) {
            const uint32_t a0 = lds32(sbase + SM_O + ks * 32 + t * 4), a2 = lds32(sbase + SM_O + ks * 32 + 16 + t * 4);
#pragma unroll
            for (int i = 0; i < 5; i++) mma16816(y[ks & 1][i], a0, a0, a2, a2, bw[ks][2 * i], bw[ks][2 * i + 1]);
        }
        if (g < 5) {
            float v0 = y[0][0][0] + y[1][0][0], v1 = y[0][0][1] + y[1][0][1];
#pragma unroll
            for (int i = 1; i < 5; i++) {
                v0 = (g == i) ? y[0][i][0] + y[1][i][0] : v0;
                v1 = (g == i) ? y[0][i][1] + y[1][i][1] : v1;
            }
            st_word2(ydst, v0, v1, tag);
        }
        if (tid == 0) TL(11);
        named_arrive(3, CONS_AUX);
    } else {
        {
            const int atid = tid - (NCONS_WARPS + 1) * 32;
            const unsigned char* wsrc = reinterpret_cast<const unsigned char*>(p.wq) + (size_t)(group * HPG * DH + r * 32) * 2;
#pragma unroll
            for (int i = 0; i < 16; i++) {
                const int row = (atid >> 2) + 40 * i, ch = atid & 3;
                cp_async16(sbase + SM_W + row * 64 + ((ch ^ ((row >> 1) & 3)) << 4), wsrc + (size_t)row * (NHEAD * DH * 2) + ch * 16);
            }
            named_sync(6, (NAUX_WARPS + 1) * 32);
            asm volatile("cp.async.mbarrier.arrive.noinc.shared::cta.b64 [%0];" ::"r"(bar_wq) : "memory");
        }
        const int col = blockIdx.x * NAUX_WARPS + (warp - NCONS_WARPS - 1);
        uint32_t xr[10];
#pragma unroll
        for (int i = 0; i < 10; i++) xr[i] = ldg32(reinterpret_cast<const uint32_t*>(p.x) + lane + 32 * i);
        const float xcol = __bfloat162float(p.x[col]);
        const unsigned tag = *reinterpret_cast<volatile unsigned*>(&g_epoch) + 1;
        const unsigned long long* ysrc = g_y + lane * D_MODEL + col;
        float xv[20];
#pragma unroll
        for (int i = 0; i < 10; i++) { xv[2 * i] = bf_lo(xr[i]); xv[2 * i + 1] = bf_hi(xr[i]); }
        const LnStat st1 = warp_layernorm(xv);
        const LnStat st2 = warp_layernorm(xv);
        const float h = ln_apply(ln_apply(xcol, st1), st2);
        float acc = 0.f;
#pragma unroll 9
        for (int i = 0; i < FDIM / 64; i++) {
            const int f2 = lane + 32 * i;
            const uint32_t w1 = ldg32(reinterpret_cast<const uint32_t*>(p.w1) + f2);
            const uint32_t b1 = ldg32(reinterpret_cast<const uint32_t*>(p.b1) + f2);
            const uint32_t w2 = ldg32(reinterpret_cast<const uint32_t*>(p.w2) + f2);
#pragma unroll
            for (int e = 0; e < 2; e++) {
                const float u = bf16r(bf16r(h * (e ? bf_hi(w1) : bf_lo(w1))) + (e ? bf_hi(b1) : bf_lo(b1)));
                const float z = 0.7978845608028654f * (u + 0.044715f * u * u * u);
                const float ge = bf16r(u * rcp(1.f + ex2(-2.f * LOG2E * z)));
                acc = fmaf(ge, e ? bf_hi(w2) : bf_lo(w2), acc);
            }
        }
        const float yb = bf16r(bf16r(warp_sum(acc)) + __bfloat162float(p.b2[0]));

        named_sync(2, CONS_AUX);
        unsigned long long w = ld_word(ysrc);
        named_sync(3, CONS_AUX);
        for (unsigned n = 0;; n++) {
            const bool ok = word_label(w) == tag;
            if (__all_sync(0xffffffffu, ok)) break;
            if (!ok) w = ld_word(ysrc);
            if (n > SPIN_LIMIT) __trap();
        }
        const float a = bf16r(warp_sum(word_value(w)));
        if (lane == 0) {
            p.out[col] = __float2bfloat16_rn(bf16r(xcol + a) + yb);
            if (col == 0) { g_total = 0; g_done = 0; *reinterpret_cast<volatile unsigned*>(&g_epoch) = tag; }
        }
        if (warp == NCONS_WARPS + 1 && lane == 0) TL(13);
    }
}

}

typedef CUresult (*EncodeTiledFn)(CUtensorMap*, CUtensorMapDataType, cuuint32_t, void*, const cuuint64_t*, const cuuint64_t*,
                                  const cuuint32_t*, const cuuint32_t*, CUtensorMapInterleave, CUtensorMapSwizzle,
                                  CUtensorMapL2promotion, CUtensorMapFloatOOBfill);

extern "C" void kernel_launch(void* const* d_in, const int* in_sizes, int n_in, void* d_out, int out_size) {
    (void)in_sizes; (void)n_in; (void)out_size;
    static EncodeTiledFn encode = nullptr;
    if (!encode) {
        void* fn = nullptr;
        cudaDriverEntryPointQueryResult qres;
        cudaGetDriverEntryPoint("cuTensorMapEncodeTiled", &fn, cudaEnableDefault, &qres);
        encode = (EncodeTiledFn)fn;
        cudaFuncSetAttribute(fused_decode_kernel, cudaFuncAttributeMaxDynamicSharedMemorySize, SM_TOTAL);
    }
    Params p;
    {
        cuuint64_t dims[2] = {D_MODEL, NHEAD * DH};
        cuuint64_t strides[1] = {D_MODEL * 2};
        cuuint32_t box[2] = {32, DH};
        cuuint32_t estr[2] = {1, 1};
        encode(&p.wo_map, CU_TENSOR_MAP_DATA_TYPE_BFLOAT16, 2, d_in[4], dims, strides, box, estr, CU_TENSOR_MAP_INTERLEAVE_NONE,
               CU_TENSOR_MAP_SWIZZLE_64B, CU_TENSOR_MAP_L2_PROMOTION_NONE, CU_TENSOR_MAP_FLOAT_OOB_FILL_NONE);
    }
    p.x = (const __nv_bfloat16*)d_in[0];
    p.k = (const __nv_bfloat16*)d_in[1];
    p.v = (const __nv_bfloat16*)d_in[2];
    p.wq = (const __nv_bfloat16*)d_in[3];
    p.wo = (const __nv_bfloat16*)d_in[4];
    p.w1 = (const __nv_bfloat16*)d_in[6];
    p.b1 = (const __nv_bfloat16*)d_in[7];
    p.w2 = (const __nv_bfloat16*)d_in[8];
    p.b2 = (const __nv_bfloat16*)d_in[9];
    p.out = (__nv_bfloat16*)d_out;
    fused_decode_kernel<<<NCTA, NTHREADS, SM_TOTAL, cudaStreamPerThread>>>(p);
}
```

```cpp
#include <cuda.h>
#include <cuda_runtime.h>
#include <cuda_bf16.h>
#include <stdint.h>

namespace {

constexpr int D_MODEL = 640;
constexpr int NHEAD = 32;
constexpr int SK = 32768;
constexpr int DH = 128;
constexpr int FDIM = 1728;

constexpr int CPH = 4;
constexpr int NCTA = NHEAD * CPH;
constexpr int STAGES = 10;
constexpr int INFLIGHT = 3;

constexpr int TILE_KEYS = 64;
constexpr int TILE_BYTES = TILE_KEYS * DH * 2;
constexpr int ITEMS = SK / TILE_KEYS;
constexpr int LEAD = 1;
constexpr int END_ITEMS = 3 * CPH, END_WINDOW = 5;
constexpr int WO_T0 = 48, WO_STEP = 18;
constexpr int NSTATIC = 2;
constexpr int GRABS_PER_LAUNCH = NHEAD * (ITEMS - NSTATIC * CPH) + NCTA;

constexpr int NCONS_WARPS = 4;
constexpr int NAUX_WARPS = 4;
constexpr int NTHREADS = (NCONS_WARPS + 1 + NAUX_WARPS) * 32;

constexpr int WO_COLS = D_MODEL / 4;
constexpr int W_BYTES = D_MODEL * 64;
constexpr int RED_STRIDE = 136;
constexpr int REC_WORDS = 132;

constexpr int SM_RING = 0;
constexpr int SM_W = SM_RING + STAGES * TILE_BYTES;
constexpr int SM_RED = SM_W + W_BYTES;
constexpr int SM_XN = SM_RED + 16 * RED_STRIDE * 4;
constexpr int SM_Q = SM_XN + D_MODEL * 2;
constexpr int SM_O = SM_Q + DH * 2;
constexpr int SM_STAT = SM_O + DH * 2;
constexpr int SM_META = SM_STAT + 64;
constexpr int SM_BAR = SM_META + 64;
constexpr int SM_TOTAL = SM_BAR + (2 * STAGES + 3) * 8;
static_assert(INFLIGHT == 3 && NSTATIC == 2 && INFLIGHT + 1 < STAGES, "start-up sequence: K0, V0, K1, then V1");
static_assert(WO_T0 + 4 * WO_STEP <= NCTA, "wo thresholds count CTAs");
static_assert(END_WINDOW < STAGES, "window");
static_assert(STAGES <= 16, "meta size");

constexpr float LOG2E = 1.4426950408889634f;
constexpr float SCORE_SCALE = 0.08838834764831845f;
constexpr float LN_EPS = 1.0013580322265625e-05f;
constexpr unsigned SPIN_LIMIT = 1u << 22;

__device__ unsigned g_epoch;
__device__ unsigned g_total;
__device__ unsigned g_done;
__device__ unsigned g_queue[NHEAD * 32];
__device__ unsigned long long g_q[NHEAD * DH];
__device__ unsigned long long g_rec[NCTA * REC_WORDS];
__device__ unsigned long long g_y[NHEAD * D_MODEL];

__device__ __forceinline__ uint32_t smem_u32(const void* p) { return (uint32_t)__cvta_generic_to_shared(p); }

__device__ __forceinline__ void mbar_init(uint32_t bar, uint32_t cnt) {
    asm volatile("mbarrier.init.shared::cta.b64 [%0], %1;" ::"r"(bar), "r"(cnt) : "memory");
}
__device__ __forceinline__ void mbar_expect_tx(uint32_t bar, uint32_t bytes) {
    asm volatile("mbarrier.arrive.expect_tx.shared::cta.b64 _, [%0], %1;" ::"r"(bar), "r"(bytes) : "memory");
}
__device__ __forceinline__ void mbar_arrive(uint32_t bar) {
    asm volatile("mbarrier.arrive.shared::cta.b64 _, [%0];" ::"r"(bar) : "memory");
}
__device__ __forceinline__ bool mbar_try(uint32_t bar, uint32_t parity) {
    uint32_t ok;
    asm volatile("{\n.reg .pred p;\nmbarrier.try_wait.parity.shared::cta.b64 p, [%1], %2;\nselp.u32 %0, 1, 0, p;\n}"
                 : "=r"(ok) : "r"(bar), "r"(parity) : "memory");
    return ok != 0;
}
__device__ __forceinline__ bool mbar_test(uint32_t bar, uint32_t parity) {
    uint32_t ok;
    asm volatile("{\n.reg .pred p;\nmbarrier.test_wait.parity.shared::cta.b64 p, [%1], %2;\nselp.u32 %0, 1, 0, p;\n}"
                 : "=r"(ok) : "r"(bar), "r"(parity) : "memory");
    return ok != 0;
}
__device__ __forceinline__ void mbar_wait(uint32_t bar, uint32_t parity) {
    unsigned n = 0;
    while (!mbar_try(bar, parity)) {
        if (++n > SPIN_LIMIT) __trap();
    }
}
__device__ __forceinline__ void bulk_g2s(uint32_t dst, const void* src, uint32_t bytes, uint32_t bar, uint64_t pol) {
    asm volatile(
        "cp.async.bulk.shared::cluster.global.mbarrier::complete_tx::bytes.L2::cache_hint [%0], [%1], %2, [%3], %4;"
        ::"r"(dst), "l"(src), "r"(bytes), "r"(bar), "l"(pol) : "memory");
}
__device__ __forceinline__ void tma_load_2d(uint32_t dst, const CUtensorMap* map, int c0, int c1, uint32_t bar) {
    asm volatile("cp.async.bulk.tensor.2d.shared::cluster.global.mbarrier::complete_tx::bytes [%0], [%1, {%3, %4}], [%2];"
                 ::"r"(dst), "l"(map), "r"(bar), "r"(c0), "r"(c1) : "memory");
}
__device__ __forceinline__ uint32_t ldg32(const void* p) {
    uint32_t v;
    asm volatile("ld.global.nc.u32 %0, [%1];" : "=r"(v) : "l"(p));
    return v;
}
__device__ __forceinline__ void cp_async16(uint32_t dst, const void* src) {
    asm volatile("cp.async.cg.shared.global [%0], [%1], 16;" ::"r"(dst), "l"(src) : "memory");
}
__device__ __forceinline__ void named_sync(int id, int n) { asm volatile("bar.sync %0, %1;" ::"r"(id), "r"(n) : "memory"); }
__device__ __forceinline__ void named_arrive(int id, int n) { asm volatile("bar.arrive %0, %1;" ::"r"(id), "r"(n) : "memory"); }

__device__ __forceinline__ uint4 lds128(uint32_t a) {
    uint4 v;
    asm volatile("ld.shared.v4.u32 {%0,%1,%2,%3}, [%4];" : "=r"(v.x), "=r"(v.y), "=r"(v.z), "=r"(v.w) : "r"(a));
    return v;
}
__device__ __forceinline__ uint32_t lds32(uint32_t a) {
    uint32_t v;
    asm volatile("ld.shared.u32 %0, [%1];" : "=r"(v) : "r"(a));
    return v;
}
__device__ __forceinline__ void sts32(uint32_t a, float v) {
    asm volatile("st.shared.f32 [%0], %1;" ::"r"(a), "f"(v) : "memory");
}
__device__ __forceinline__ void ldsm4t(uint32_t (&r)[4], uint32_t a) {
    asm volatile("ldmatrix.sync.aligned.m8n8.x4.trans.shared.b16 {%0,%1,%2,%3}, [%4];"
                 : "=r"(r[0]), "=r"(r[1]), "=r"(r[2]), "=r"(r[3]) : "r"(a));
}
__device__ __forceinline__ void mma16816(float (&c)[4], uint32_t a0, uint32_t a1, uint32_t a2, uint32_t a3, uint32_t b0, uint32_t b1) {
    asm volatile(
        "mma.sync.aligned.m16n8k16.row.col.f32.bf16.bf16.f32 {%0,%1,%2,%3}, {%4,%5,%6,%7}, {%8,%9}, {%0,%1,%2,%3};"
        : "+f"(c[0]), "+f"(c[1]), "+f"(c[2]), "+f"(c[3]) : "r"(a0), "r"(a1), "r"(a2), "r"(a3), "r"(b0), "r"(b1));
}
__device__ __forceinline__ float bf16r(float x) { return __bfloat162float(__float2bfloat16_rn(x)); }
__device__ __forceinline__ float bf_lo(uint32_t v) { return __uint_as_float(v << 16); }
__device__ __forceinline__ float bf_hi(uint32_t v) { return __uint_as_float(v & 0xffff0000u); }
__device__ __forceinline__ uint32_t pack_bf16(float lo, float hi) {
    uint32_t r;
    asm("cvt.rn.bf16x2.f32 %0, %1, %2;" : "=r"(r) : "f"(hi), "f"(lo));
    return r;
}
__device__ __forceinline__ float ex2(float x) { float y; asm("ex2.approx.ftz.f32 %0, %1;" : "=f"(y) : "f"(x)); return y; }
__device__ __forceinline__ float rcp(float x) { float y; asm("rcp.approx.ftz.f32 %0, %1;" : "=f"(y) : "f"(x)); return y; }

__device__ __forceinline__ void st_word(unsigned long long* p, float v, unsigned label) {
    unsigned long long w = ((unsigned long long)label << 32) | __float_as_uint(v);
    asm volatile("st.relaxed.gpu.global.b64 [%0], %1;" ::"l"(p), "l"(w) : "memory");
}
__device__ __forceinline__ void st_word2(unsigned long long* p, float v0, float v1, unsigned label) {
    const unsigned long long w0 = ((unsigned long long)label << 32) | __float_as_uint(v0);
    const unsigned long long w1 = ((unsigned long long)label << 32) | __float_as_uint(v1);
    asm volatile("st.relaxed.gpu.global.v2.b64 [%0], {%1, %2};" ::"l"(p), "l"(w0), "l"(w1) : "memory");
}
__device__ __forceinline__ unsigned long long ld_word(const unsigned long long* p) {
    unsigned long long w;
    asm volatile("ld.relaxed.gpu.global.b64 %0, [%1];" : "=l"(w) : "l"(p) : "memory");
    return w;
}
__device__ __forceinline__ float word_value(unsigned long long w) { return __uint_as_float((unsigned)w); }
__device__ __forceinline__ unsigned word_label(unsigned long long w) { return (unsigned)(w >> 32); }

__device__ __forceinline__ float warp_sum(float v) {
#pragma unroll
    for (int o = 16; o > 0; o >>= 1) v += __shfl_xor_sync(0xffffffffu, v, o);
    return v;
}

struct LnStat { float mean, den; };
__device__ __forceinline__ float ln_apply(float x, LnStat st) { return bf16r(__fdiv_rn(bf16r(x - st.mean), st.den)); }
__device__ __forceinline__ LnStat warp_layernorm(float (&v)[20]) {
    float s = 0.f;
#pragma unroll
    for (int i = 0; i < 20; i++) s += v[i];
    const float mean = warp_sum(s) / (float)D_MODEL;
    float ss = 0.f;
#pragma unroll
    for (int i = 0; i < 20; i++) { float d = v[i] - mean; ss += d * d; }
    const float var = bf16r(warp_sum(ss) / (float)D_MODEL);
    LnStat st;
    st.mean = bf16r(mean);
    st.den = bf16r(sqrtf(bf16r(var + LN_EPS)));
#pragma unroll
    for (int i = 0; i < 20; i++) v[i] = ln_apply(v[i], st);
    return st;
}

struct Params {
    CUtensorMap wo_map;
    const __nv_bfloat16 *x, *k, *v, *wq, *w1, *b1, *w2, *b2;
    __nv_bfloat16* out;
};

__device__ __forceinline__ void flush_record(unsigned char* smem, unsigned long long* rec, unsigned tag16, const uint32_t (&ra)[4],
                                             int warp, int lane, int tid, float (&acc)[8][4], float m, float l,
                                             unsigned long long& own_o, unsigned long long& own_l) {
    float* red = reinterpret_cast<float*>(smem + SM_RED);
    float* stat = reinterpret_cast<float*>(smem + SM_STAT);
    if (lane == 0) { stat[warp] = m; stat[4 + warp] = l; }
#pragma unroll
    for (int c = 0; c < 8; c++) {
        sts32(ra[c >> 1] + (c & 1) * 32, acc[c][0] + acc[c ^ 1][1]);
        sts32(ra[c >> 1] + (c & 1) * 32 + 256, acc[c][2] + acc[c ^ 1][3]);
    }
    named_sync(1, 128);
    float mw[4], M = -INFINITY;
#pragma unroll
    for (int w = 0; w < 4; w++) { mw[w] = stat[w]; M = fmaxf(M, mw[w]); }
    const float ML = (M == -INFINITY) ? 0.f : __fmul_rn(M, LOG2E);
    float o = 0.f, L = 0.f;
#pragma unroll
    for (int w = 0; w < 4; w++) {
        const float f = ex2(__fmul_rn(mw[w], LOG2E) - ML);
        float s = 0.f;
#pragma unroll
        for (int tt = 0; tt < 4; tt++) s += red[(w * 4 + tt) * RED_STRIDE + tid];
        o += f * s;
        L += f * stat[4 + w];
    }
    const unsigned label = (tag16 << 16) | (__float_as_uint(M) >> 16);
    st_word(rec + tid, o, label);
    if (tid == 0) st_word(rec + 128, L, label);
    own_o = ((unsigned long long)label << 32) | __float_as_uint(o);
    own_l = ((unsigned long long)label << 32) | __float_as_uint(L);
}

__global__ void __launch_bounds__(NTHREADS, 1) fused_decode_kernel(const __grid_constant__ Params p) {
    extern __shared__ __align__(1024) unsigned char smem[];
    const int tid = threadIdx.x, warp = tid >> 5, lane = tid & 31;
    const int head = blockIdx.x / CPH, r = blockIdx.x % CPH;
    const uint32_t sbase = smem_u32(smem);
    const uint32_t bar_full = sbase + SM_BAR, bar_empty = bar_full + STAGES * 8;
    const uint32_t bar_wq = bar_empty + STAGES * 8, bar_wo = bar_wq + 8, bar_wfree = bar_wo + 8;
    volatile int* meta = reinterpret_cast<volatile int*>(smem + SM_META);
    volatile unsigned* s_tag = reinterpret_cast<volatile unsigned*>(smem + SM_STAT + 32);
    const unsigned char* kg = reinterpret_cast<const unsigned char*>(p.k) + (size_t)head * SK * DH * 2;
    const unsigned char* vg = reinterpret_cast<const unsigned char*>(p.v) + (size_t)head * SK * DH * 2;
    const int ntask = (blockIdx.x < D_MODEL / 4 - NCTA) ? 2 : 1;
    const int tail_count = NCONS_WARPS * 32 + ntask * 32;
    uint64_t pol;
    asm volatile("createpolicy.fractional.L2::evict_first.b64 %0, 1.0;" : "=l"(pol));

    if (warp == NCONS_WARPS) {
        if (lane == 0) {
            for (int s = 0; s < INFLIGHT; s++) mbar_init(bar_full + s * 8, 1);
            asm volatile("fence.mbarrier_init.release.cluster;" ::: "memory");
#pragma unroll
            for (int n = 0; n < INFLIGHT; n++) {
                mbar_expect_tx(bar_full + n * 8, TILE_BYTES);
                bulk_g2s(sbase + SM_RING + n * TILE_BYTES, ((n & 1) ? vg : kg) + (size_t)(r + (n >> 1) * CPH) * TILE_BYTES, TILE_BYTES, bar_full + n * 8, pol);
            }
            for (int s = 0; s < STAGES; s++) {
                if (s >= INFLIGHT) mbar_init(bar_full + s * 8, 1);
                mbar_init(bar_empty + s * 8, NCONS_WARPS);
            }
            mbar_init(bar_wq, NAUX_WARPS * 32); mbar_init(bar_wo, 1); mbar_init(bar_wfree, NCONS_WARPS);
            asm volatile("fence.mbarrier_init.release.cluster;" ::: "memory");
            meta[0] = meta[1] = meta[2] = 1;
        }
        __syncwarp();
        named_arrive(5, (NCONS_WARPS + 1) * 32);
        named_arrive(6, (NAUX_WARPS + 1) * 32);
        if (lane == 0) {
            unsigned* queue = g_queue + head * 32;
            unsigned next = atomicAdd(queue, 1u) + NSTATIC * CPH;
            unsigned total = atomicAdd(&g_total, 1u);
            const unsigned epoch = *reinterpret_cast<volatile unsigned*>(&g_epoch);
            const unsigned total_base = epoch * (unsigned)GRABS_PER_LAUNCH, done_base = epoch * (unsigned)NCTA;
            int n = INFLIGHT;
            int window = INFLIGHT;
            auto issue = [&](const unsigned char* src) {
                const int s = n % STAGES;
                const int q = max(n - window, 0);
                mbar_wait(bar_full + (q % STAGES) * 8, (q / STAGES) & 1);
                if (n >= STAGES) mbar_wait(bar_empty + s * 8, ((n / STAGES) - 1) & 1);
                meta[s] = 1;
                mbar_expect_tx(bar_full + s * 8, TILE_BYTES);
                bulk_g2s(sbase + SM_RING + s * TILE_BYTES, src, TILE_BYTES, bar_full + s * 8, pol);
                n++;
            };
            issue(vg + (size_t)(r + CPH) * TILE_BYTES);
#pragma unroll 1
            while (next < (unsigned)ITEMS) {
                const unsigned item = next;
                const int lead = (int)(item - NSTATIC * CPH) - (int)((total - total_base) / NHEAD);
                window = INFLIGHT + (lead > LEAD ? -1 : (lead < -LEAD ? 1 : 0));
                if (item + END_ITEMS >= (unsigned)ITEMS) window = END_WINDOW;
                next = atomicAdd(queue, 1u) + NSTATIC * CPH;
                total = atomicAdd(&g_total, 1u);
                issue(kg + (size_t)item * TILE_BYTES);
                issue(vg + (size_t)item * TILE_BYTES);
            }
            const int s = n % STAGES;
            if (n >= STAGES) mbar_wait(bar_empty + s * 8, ((n / STAGES) - 1) & 1);
            meta[s] = 0;
            mbar_arrive(bar_full + s * 8);

            unsigned done = atomicAdd(&g_done, 1u) + 1 - done_base, spins = 0;
            mbar_wait(bar_wfree, 0);
            mbar_expect_tx(bar_wo, W_BYTES);
#pragma unroll 1
            for (int i = 0; i < 5; i++) {
                while (done < (unsigned)(WO_T0 + i * WO_STEP)) {
                    done = *reinterpret_cast<volatile unsigned*>(&g_done) - done_base;
                    if (++spins > SPIN_LIMIT) __trap();
                }
                tma_load_2d(sbase + SM_W + i * DH * 64, &p.wo_map, r * WO_COLS + i * 32, head * DH, bar_wo);
            }
        }
    } else if (warp < NCONS_WARPS) {
        const int g = lane >> 2, t = lane & 3, par = g & 1;
        unsigned tag;
        {
            uint32_t xr[10];
#pragma unroll
            for (int i = 0; i < 10; i++) xr[i] = ldg32(reinterpret_cast<const uint32_t*>(p.x) + lane + 32 * i);
            tag = *reinterpret_cast<volatile unsigned*>(&g_epoch) + 1;
            if (warp == 0) st_word(g_q + head * DH + r * 32 + lane, 0.f, 0u);
            st_word(g_rec + blockIdx.x * REC_WORDS + tid, 0.f, 0u);
            if (tid < REC_WORDS - 128) st_word(g_rec + blockIdx.x * REC_WORDS + 128 + tid, 0.f, 0u);
            if (tid < WO_COLS / 2) st_word2(g_y + head * D_MODEL + r * WO_COLS + 2 * tid, 0.f, 0.f, 0u);
            float xv[20];
#pragma unroll
            for (int i = 0; i < 10; i++) { xv[2 * i] = bf_lo(xr[i]); xv[2 * i + 1] = bf_hi(xr[i]); }
            warp_layernorm(xv);
            if (warp == 0) {
#pragma unroll
                for (int i = 0; i < 10; i++)
                    reinterpret_cast<uint32_t*>(smem + SM_XN)[lane + 32 * i] = pack_bf16(xv[2 * i], xv[2 * i + 1]);
            }
            named_sync(5, (NCONS_WARPS + 1) * 32);
            mbar_wait(bar_wq, 0);
            float c[4][4];
#pragma unroll
            for (int i = 0; i < 4; i++) { c[i][0] = c[i][1] = c[i][2] = c[i][3] = 0.f; }
            const uint32_t xa = sbase + SM_XN + t * 4;
#pragma unroll
            for (int kk = 0; kk < 20; kk++) {
                const int row = kk * 32 + lane;
                uint32_t b[4];
                ldsm4t(b, sbase + SM_W + row * 64 + ((warp ^ ((row >> 1) & 3)) << 4));
                const uint32_t a0 = lds32(xa + kk * 64), a2 = lds32(xa + kk * 64 + 16);
                const uint32_t a4 = lds32(xa + kk * 64 + 32), a6 = lds32(xa + kk * 64 + 48);
                mma16816(c[(2 * kk) & 3], a0, a0, a2, a2, b[0], b[1]);
                mma16816(c[(2 * kk + 1) & 3], a4, a4, a6, a6, b[2], b[3]);
            }
            __syncwarp();
            if (lane == 0) mbar_arrive(bar_wfree);
            if (g == 0) {
                unsigned long long* dst = g_q + head * DH + r * 32 + warp * 8 + 2 * t;
                st_word(dst, bf16r(c[0][0] + c[1][0] + c[2][0] + c[3][0]), tag);
                st_word(dst + 1, bf16r(c[0][1] + c[1][1] + c[2][1] + c[3][1]), tag);
            }
            const unsigned long long* qsrc = g_q + head * DH + tid;
            unsigned long long w = ld_word(qsrc);
            for (unsigned n = 0;; n++) {
                const bool ok = word_label(w) == tag;
                if (__all_sync(0xffffffffu, ok)) break;
                if (!ok) w = ld_word(qsrc);
                if (n > SPIN_LIMIT) __trap();
            }
            reinterpret_cast<__nv_bfloat16*>(smem + SM_Q)[tid] = __float2bfloat16_rn(word_value(w));
            named_sync(1, 128);
        }
        unsigned tag16 = tag % 65535u + 1u;
        unsigned long long* myrec = g_rec + blockIdx.x * REC_WORDS;
        const unsigned long long* rec = g_rec + head * CPH * REC_WORDS + tid;
        const unsigned long long* recl = g_rec + head * CPH * REC_WORDS + 128;
        unsigned long long* ydst = g_y + head * D_MODEL + r * WO_COLS + 16 * warp + 64 * (t >> 1) + 8 * (t & 1) + g;
        uint32_t ra[4];
#pragma unroll
        for (int k = 0; k < 4; k++) ra[k] = sbase + SM_RED + ((warp * 4 + t) * RED_STRIDE + g + (k ^ t) * 16) * 4;
        asm volatile("" : "+r"(tag16), "+l"(myrec), "+l"(rec), "+l"(recl), "+l"(ydst));
        asm volatile("" : "+r"(ra[0]), "+r"(ra[1]), "+r"(ra[2]), "+r"(ra[3]));

        const uint32_t koff = SM_RING + (warp * 16 + g) * 256 + (par << 6) + t * 16;
        const uint32_t voff = SM_RING + (warp * 16 + (lane & 7) + 8 * (lane >> 4)) * 256 + ((lane >> 3) & 1) * 128 + (lane & 7) * 16;
        const bool diag = (t == (g >> 1));
        const uint32_t sel0 = diag ? (par ? 0x1044u : 0x4410u) : 0x4444u;
        const uint32_t sel1 = diag ? (par ? 0x3244u : 0x4432u) : 0x4444u;

        float acc[8][4];
        uint32_t qf[4][4];
#pragma unroll
        for (int c = 0; c < 8; c++) { acc[c][0] = acc[c][1] = acc[c][2] = acc[c][3] = 0.f; }
#pragma unroll
        for (int u = 0; u < 4; u++) {
            const uint4 v = lds128(sbase + SM_Q + (((par << 6) + t * 16) ^ (u << 6)));
            qf[u][0] = v.x; qf[u][1] = v.y; qf[u][2] = v.z; qf[u][3] = v.w;
        }
        float m = -INFINITY, mL = 0.f, l = 0.f, lw = 0.f;
        int s = 0;
        uint32_t ph = 0;
#pragma unroll 1
        while (true) {
            mbar_wait(bar_full + s * 8, ph);
            if (meta[s] == 0) break;
            const uint32_t ka = sbase + s * TILE_BYTES + koff;
            uint4 x[4], y[4];
#pragma unroll
            for (int u = 0; u < 4; u++) { x[u] = lds128(ka ^ (u << 6)); y[u] = lds128((ka ^ (u << 6)) + 2048); }
            float c0[4] = {0.f, 0.f, 0.f, 0.f}, c1[4] = {0.f, 0.f, 0.f, 0.f};
#pragma unroll
            for (int u = 0; u < 4; u++) {
                mma16816(c0, x[u].x, y[u].x, x[u].y, y[u].y, qf[u][0], qf[u][1]);
                mma16816(c1, x[u].z, y[u].z, x[u].w, y[u].w, qf[u][2], qf[u][3]);
            }
            __syncwarp();
            if (lane == 0) mbar_arrive(bar_empty + s * 8);
            if (++s == STAGES) { s = 0; ph ^= 1; }

            float s_lo = par ? (c0[1] + c1[1]) : (c0[0] + c1[0]);
            float s_hi = par ? (c0[3] + c1[3]) : (c0[2] + c1[2]);
            {
                uint32_t pk = pack_bf16(s_lo, s_hi);
                pk = pack_bf16(bf_lo(pk) * SCORE_SCALE, bf_hi(pk) * SCORE_SCALE);
                s_lo = bf_lo(pk); s_hi = bf_hi(pk);
            }
            const float mx = fmaxf(s_lo, s_hi);
            if (__any_sync(0xffffffffu, mx > m)) {
                float mn = fmaxf(mx, m);
                mn = fmaxf(mn, __shfl_xor_sync(0xffffffffu, mn, 4));
                mn = fmaxf(mn, __shfl_xor_sync(0xffffffffu, mn, 8));
                mn = fmaxf(mn, __shfl_xor_sync(0xffffffffu, mn, 16));
                const float mLn = __fmul_rn(mn, LOG2E);
                const float sc = (m == -INFINITY) ? 0.f : ex2(mL - mLn);
#pragma unroll
                for (int c = 0; c < 8; c++) { acc[c][0] *= sc; acc[c][1] *= sc; acc[c][2] *= sc; acc[c][3] *= sc; }
                l *= sc;
                m = mn; mL = mLn;
            }
            const float p_lo = ex2(fmaf(s_lo, LOG2E, -mL));
            const float p_hi = ex2(fmaf(s_hi, LOG2E, -mL));
            l += p_lo + p_hi;
            lw = l + __shfl_xor_sync(0xffffffffu, l, 4);
            lw += __shfl_xor_sync(0xffffffffu, lw, 8);
            lw += __shfl_xor_sync(0xffffffffu, lw, 16);
            const uint32_t pk = pack_bf16(p_lo, p_hi);
            const uint32_t b0 = __byte_perm(pk, 0, sel0), b1 = __byte_perm(pk, 0, sel1);

            mbar_wait(bar_full + s * 8, ph);
            const uint32_t va = sbase + s * TILE_BYTES + voff;
#pragma unroll
            for (int c = 0; c < 8; c++) {
                uint32_t a[4];
                ldsm4t(a, va ^ (c << 4));
                mma16816(acc[c], a[0], a[1], a[2], a[3], b0, b1);
            }
            __syncwarp();
            if (lane == 0) mbar_arrive(bar_empty + s * 8);
            if (++s == STAGES) { s = 0; ph ^= 1; }
        }
        if (tid == 0) *s_tag = tag;
        named_arrive(2, tail_count);
        unsigned long long wo_[CPH], wl[CPH];
        unsigned long long own_o, own_l;
        flush_record(smem, myrec, tag16, ra, warp, lane, tid, acc, m, lw, own_o, own_l);

#pragma unroll
        for (int i = 0; i < CPH; i++) {
            if (i == r) { wo_[i] = own_o; wl[i] = own_l; }
            else { wo_[i] = ld_word(rec + i * REC_WORDS); wl[i] = ld_word(recl + i * REC_WORDS); }
        }
        uint32_t aw[3][8][4];
        auto load_wo_frags = [&]() {
#pragma unroll
            for (int i = 0; i < 3; i++) {
                if (i < 2 || warp < 2) {
                    const int nt = 2 * (warp + 4 * i) + ((lane >> 3) & 1), row = (lane & 7) + 8 * (lane >> 4);
                    const uint32_t wa = sbase + SM_W + (nt >> 2) * (DH * 64) + row * 64 + (((nt & 3) ^ ((row >> 1) & 3)) << 4);
#pragma unroll
                    for (int ks = 0; ks < 8; ks++) ldsm4t(aw[i][ks], wa + ks * 16 * 64);
                }
            }
        };
        bool frags = false;
        for (unsigned n = 0;; n++) {
            if (!frags && __all_sync(0xffffffffu, mbar_test(bar_wo, 0))) { load_wo_frags(); frags = true; }
            bool ok = true;
#pragma unroll
            for (int i = 0; i < CPH; i++) {
                if ((word_label(wo_[i]) >> 16) != tag16) { wo_[i] = ld_word(rec + i * REC_WORDS); ok = false; }
                if ((word_label(wl[i]) >> 16) != tag16) { wl[i] = ld_word(recl + i * REC_WORDS); ok = false; }
            }
            if (__all_sync(0xffffffffu, ok)) break;
            if (n > SPIN_LIMIT) __trap();
        }
        if (r == 0 && tid == 0) g_queue[head * 32] = 0;
        {
            float M = -INFINITY;
#pragma unroll
            for (int i = 0; i < CPH; i++) M = fmaxf(M, __uint_as_float(word_label(wo_[i]) << 16));
            const float ML = __fmul_rn(M, LOG2E);
            float o = 0.f, L = 0.f;
#pragma unroll
            for (int i = 0; i < CPH; i++) {
                const float f = ex2(__fmul_rn(__uint_as_float(word_label(wo_[i]) << 16), LOG2E) - ML);
                o = fmaf(f, word_value(wo_[i]), o);
                L = fmaf(f, word_value(wl[i]), L);
            }
            reinterpret_cast<__nv_bfloat16*>(smem + SM_O)[tid] = __float2bfloat16_rn(__fdividef(o, L));
        }
        named_sync(1, 128);
        if (!frags) { mbar_wait(bar_wo, 0); load_wo_frags(); }
        float y[3][2][4];
#pragma unroll
        for (int i = 0; i < 3; i++) {
            y[i][0][0] = y[i][0][1] = y[i][0][2] = y[i][0][3] = 0.f;
            y[i][1][0] = y[i][1][1] = y[i][1][2] = y[i][1][3] = 0.f;
        }
#pragma unroll
        for (int ks = 0; ks < 8; ks++) {
            const uint32_t b0 = lds32(sbase + SM_O + ks * 32 + t * 4), b1 = lds32(sbase + SM_O + ks * 32 + 16 + t * 4);
#pragma unroll
            for (int i = 0; i < 3; i++)
                if (i < 2 || warp < 2) mma16816(y[i][ks & 1], aw[i][ks][0], aw[i][ks][1], aw[i][ks][2], aw[i][ks][3], b0, b1);
        }
        {
            const float lo0 = y[0][0][0] + y[0][1][0], hi0 = y[0][0][2] + y[0][1][2];
            const float lo1 = y[1][0][0] + y[1][1][0], hi1 = y[1][0][2] + y[1][1][2];
            st_word(ydst, (t & 2) ? ((t & 1) ? hi1 : lo1) : ((t & 1) ? hi0 : lo0), tag);
            if (warp < 2 && t < 2) st_word(ydst + 128, (t & 1) ? y[2][0][2] + y[2][1][2] : y[2][0][0] + y[2][1][0], tag);
        }
        named_arrive(3, tail_count);
    } else {
        {
            constexpr int RPP = NAUX_WARPS * 8;
            const int atid = tid - (NCONS_WARPS + 1) * 32, row0 = atid >> 2, ch = atid & 3;
            const unsigned char* wsrc = reinterpret_cast<const unsigned char*>(p.wq) + (size_t)(head * DH + r * 32) * 2 +
                                        (size_t)row0 * (NHEAD * DH * 2) + ch * 16;
            const uint32_t wdst = sbase + SM_W + row0 * 64 + ((ch ^ ((row0 >> 1) & 3)) << 4);
#pragma unroll
            for (int i = 0; i < (D_MODEL + RPP - 1) / RPP; i++)
                if ((i + 1) * RPP <= D_MODEL || row0 < D_MODEL - i * RPP)
                    cp_async16(wdst + i * RPP * 64, wsrc + (size_t)i * RPP * (NHEAD * DH * 2));
            named_sync(6, (NAUX_WARPS + 1) * 32);
            asm volatile("cp.async.mbarrier.arrive.noinc.shared::cta.b64 [%0];" ::"r"(bar_wq) : "memory");
        }
        const int aw = warp - NCONS_WARPS - 1;
        if (aw < ntask) {
            const int col0 = 4 * (blockIdx.x + aw * NCTA), c = lane & 3, hs = lane >> 2;
            uint32_t xr[10];
#pragma unroll
            for (int i = 0; i < 10; i++) xr[i] = ldg32(reinterpret_cast<const uint32_t*>(p.x) + lane + 32 * i);
            const uint32_t xc0 = ldg32(p.x + col0), xc1 = ldg32(p.x + col0 + 2);
            float xv[20];
#pragma unroll
            for (int i = 0; i < 10; i++) { xv[2 * i] = bf_lo(xr[i]); xv[2 * i + 1] = bf_hi(xr[i]); }
            const LnStat st1 = warp_layernorm(xv);
            const LnStat st2 = warp_layernorm(xv);
            const float xcol[4] = {bf_lo(xc0), bf_hi(xc0), bf_lo(xc1), bf_hi(xc1)};
            float h[4], acc[4];
#pragma unroll
            for (int e = 0; e < 4; e++) { h[e] = ln_apply(ln_apply(xcol[e], st1), st2); acc[e] = 0.f; }
#pragma unroll 3
            for (int i = 0; i < FDIM / 64; i++) {
                const int f2 = lane + 32 * i;
                const uint32_t w1 = ldg32(reinterpret_cast<const uint32_t*>(p.w1) + f2);
                const uint32_t b1 = ldg32(reinterpret_cast<const uint32_t*>(p.b1) + f2);
                const uint32_t w2 = ldg32(reinterpret_cast<const uint32_t*>(p.w2) + f2);
#pragma unroll
                for (int hl = 0; hl < 2; hl++) {
                    const float w1f = hl ? bf_hi(w1) : bf_lo(w1), b1f = hl ? bf_hi(b1) : bf_lo(b1), w2f = hl ? bf_hi(w2) : bf_lo(w2);
#pragma unroll
                    for (int e = 0; e < 4; e++) {
                        const float u = bf16r(bf16r(h[e] * w1f) + b1f);
                        const float z = 0.7978845608028654f * (u + 0.044715f * u * u * u);
                        const float ge = bf16r(u * rcp(1.f + ex2(-2.f * LOG2E * z)));
                        acc[e] = fmaf(ge, w2f, acc[e]);
                    }
                }
            }
            const float b2 = __bfloat162float(p.b2[0]);
            float yb = 0.f, xo = 0.f;
#pragma unroll
            for (int e = 0; e < 4; e++) {
                const float t = bf16r(bf16r(warp_sum(acc[e])) + b2);
                yb = (c == e) ? t : yb;
                xo = (c == e) ? xcol[e] : xo;
            }

            const unsigned long long* ysrc = g_y + hs * D_MODEL + col0 + c;
            unsigned long long w[4];
            named_sync(2, tail_count);
            const unsigned tag = *s_tag;
#pragma unroll
            for (int i = 0; i < 4; i++) w[i] = ld_word(ysrc + i * 8 * D_MODEL);
            named_sync(3, tail_count);
            for (unsigned n = 0;; n++) {
                bool ok = true;
#pragma unroll
                for (int i = 0; i < 4; i++) {
                    if (word_label(w[i]) != tag) { w[i] = ld_word(ysrc + i * 8 * D_MODEL); ok = false; }
                }
                if (__all_sync(0xffffffffu, ok)) break;
                if (n > SPIN_LIMIT) __trap();
            }
            float a = (word_value(w[0]) + word_value(w[1])) + (word_value(w[2]) + word_value(w[3]));
            a += __shfl_xor_sync(0xffffffffu, a, 4);
            a += __shfl_xor_sync(0xffffffffu, a, 8);
            a += __shfl_xor_sync(0xffffffffu, a, 16);
            if (lane < 4) p.out[col0 + c] = __float2bfloat16_rn(bf16r(xo + bf16r(a)) + yb);
            if (col0 == 0 && lane == 0) *reinterpret_cast<volatile unsigned*>(&g_epoch) = tag;
        }
    }
}

}

typedef CUresult (*EncodeTiledFn)(CUtensorMap*, CUtensorMapDataType, cuuint32_t, void*, const cuuint64_t*, const cuuint64_t*,
                                  const cuuint32_t*, const cuuint32_t*, CUtensorMapInterleave, CUtensorMapSwizzle,
                                  CUtensorMapL2promotion, CUtensorMapFloatOOBfill);

extern "C" void kernel_launch(void* const* d_in, const int* in_sizes, int n_in, void* d_out, int out_size) {
    (void)in_sizes; (void)n_in; (void)out_size;
    static EncodeTiledFn encode = nullptr;
    if (!encode) {
        void* fn = nullptr;
        cudaDriverEntryPointQueryResult qres;
        cudaGetDriverEntryPoint("cuTensorMapEncodeTiled", &fn, cudaEnableDefault, &qres);
        encode = (EncodeTiledFn)fn;
        cudaFuncSetAttribute(fused_decode_kernel, cudaFuncAttributeMaxDynamicSharedMemorySize, SM_TOTAL);
    }
    Params p;
    {
        cuuint64_t dims[2] = {D_MODEL, NHEAD * DH};
        cuuint64_t strides[1] = {D_MODEL * 2};
        cuuint32_t box[2] = {32, DH};
        cuuint32_t estr[2] = {1, 1};
        encode(&p.wo_map, CU_TENSOR_MAP_DATA_TYPE_BFLOAT16, 2, d_in[4], dims, strides, box, estr, CU_TENSOR_MAP_INTERLEAVE_NONE,
               CU_TENSOR_MAP_SWIZZLE_64B, CU_TENSOR_MAP_L2_PROMOTION_NONE, CU_TENSOR_MAP_FLOAT_OOB_FILL_NONE);
    }
    p.x = (const __nv_bfloat16*)d_in[0];
    p.k = (const __nv_bfloat16*)d_in[1];
    p.v = (const __nv_bfloat16*)d_in[2];
    p.wq = (const __nv_bfloat16*)d_in[3];
    p.w1 = (const __nv_bfloat16*)d_in[6];
    p.b1 = (const __nv_bfloat16*)d_in[7];
    p.w2 = (const __nv_bfloat16*)d_in[8];
    p.b2 = (const __nv_bfloat16*)d_in[9];
    p.out = (__nv_bfloat16*)d_out;
    fused_decode_kernel<<<NCTA, NTHREADS, SM_TOTAL, cudaStreamPerThread>>>(p);
}
```
